```python
import torch

def _softmax(x, axis=-1):
    return torch.softmax(x, dim=axis)

def _gelu(x):
    return torch.nn.functional.gelu(x, approximate='tanh')

def _silu(x):
    return torch.nn.functional.silu(x)

def _sigmoid(x):
    return torch.sigmoid(x)

def _layernorm(x, axis=-1, eps=1e-05):
    m = x.mean(dim=axis, keepdim=True)
    v = x.var(dim=axis, keepdim=True, unbiased=False)
    return (x - m) / torch.sqrt(v + eps)

def _scatter_add(tgt, idx, src, axis=0):
    return tgt.clone().index_add_(axis, idx, src)

def _segment_sum(src, seg, n):
    out = torch.zeros((n,) + src.shape[1:], dtype=src.dtype)
    return out.index_add_(0, seg, src)

def _pad(x, pw):
    flat = tuple((v for pair in reversed(pw) for v in pair))
    return torch.nn.functional.pad(x, flat)
kernel_name = 'standalone__autoregressive_conv_wavernn__speech'

def setup_inputs():

    _w = lambda a: (lambda t: t.to(torch.bfloat16) if t.is_floating_point() else t)(torch.as_tensor(a))
    B, T, D, K = (2, 1000, 512, 15)
    return {'x': _w((lambda *s: torch.randn(*s, dtype=torch.bfloat16) * 0.05)(B, T, D)), 'w': _w((lambda *s: torch.randn(*s, dtype=torch.bfloat16) * 0.05)(K, D, 2 * D))}

def reference(x, w):
    B, T, D = x.shape
    K = w.shape[0]
    dil = 2
    pad = (K - 1) * dil
    xp = _pad(x, ((0, 0), (pad, 0), (0, 0)))
    h = torch.einsum('btd,de->bte', xp[:, 0:T, :], w[0])
    for i in range(1, K):
        h = h + torch.einsum('btd,de->bte', xp[:, i * dil:i * dil + T, :], w[i])
    f, g = (h[..., :D].clone(), h[..., D:].clone())
    return torch.tanh(f) * _sigmoid(g)
```

```cpp
#include <cuda_runtime.h>
#include <cuda_bf16.h>
#include <cuda.h>
#include <stdint.h>

#define NWG 1
#define STAGES 16

#define STAMP(i)
#define STAMPG(i)
namespace {

constexpr int T_ = 1000, D_ = 512, KT = 15;
constexpr int TILE_T = 256;
constexpr int XROWS = 288;
constexpr int XBYTES = XROWS * 128;
constexpr int WSTAGE = 8192;
constexpr int NCHUNK = 8;
constexpr int NITER = NCHUNK * KT;
constexpr int SM_X = 0;
constexpr int SM_W = 2 * XBYTES;
constexpr int SM_BAR = SM_W + STAGES * WSTAGE;
constexpr int SM_TOTAL = SM_BAR + 512 + 1024;
constexpr int NTHREADS = NWG * 128 + 32;
constexpr int NCOLS = TILE_T / NWG;
constexpr int NACC = NCOLS / 2;

__device__ __forceinline__ uint32_t smem_u32(const void* p) { return (uint32_t)__cvta_generic_to_shared(p); }
__device__ __forceinline__ void mbar_init(uint32_t bar, uint32_t cnt) {
    asm volatile("mbarrier.init.shared::cta.b64 [%0], %1;" ::"r"(bar), "r"(cnt) : "memory");
}
__device__ __forceinline__ void mbar_expect_tx(uint32_t bar, uint32_t bytes) {
    asm volatile("mbarrier.arrive.expect_tx.shared::cta.b64 _, [%0], %1;" ::"r"(bar), "r"(bytes) : "memory");
}
__device__ __forceinline__ void mbar_arrive(uint32_t bar) {
    asm volatile("mbarrier.arrive.shared::cta.b64 _, [%0];" ::"r"(bar) : "memory");
}
__device__ __forceinline__ void mbar_arrive_cluster(uint32_t bar, uint32_t cta) {
    asm volatile(
        "{\n.reg .b32 ra;\nmapa.shared::cluster.u32 ra, %0, %1;\n"
        "mbarrier.arrive.shared::cluster.b64 _, [ra];\n}" ::"r"(bar), "r"(cta) : "memory");
}
__device__ __forceinline__ void mbar_wait(uint32_t bar, uint32_t parity) {
    asm volatile(
        "{\n.reg .pred p;\n.reg .b32 n;\n"
        "mov.b32 n, 0;\n"
        "LAB_WAIT:\n"
        "mbarrier.try_wait.parity.shared::cta.b64 p, [%0], %1;\n"
        "@p bra LAB_DONE;\n"
        "add.u32 n, n, 1;\n"
        "setp.lt.u32 p, n, 0x400000;\n"
        "@p bra LAB_WAIT;\n"
        "trap;\n"
        "LAB_DONE:\n}" ::"r"(bar), "r"(parity) : "memory");
}
#define mbar_wait_cluster mbar_wait
__device__ __forceinline__ void mbar_arrive_pred(uint32_t bar, bool pred) {
    asm volatile("{\n.reg .pred p;\nsetp.ne.b32 p, %1, 0;\n@p mbarrier.arrive.shared::cta.b64 _, [%0];\n}" ::"r"(bar), "r"((int)pred) : "memory");
}
__device__ __forceinline__ void mbar_arrive_cluster_pred(uint32_t bar, uint32_t cta, bool pred) {
    asm volatile(
        "{\n.reg .b32 ra;\n.reg .pred p;\nsetp.ne.b32 p, %2, 0;\nmapa.shared::cluster.u32 ra, %0, %1;\n"
        "@p mbarrier.arrive.shared::cluster.b64 _, [ra];\n}" ::"r"(bar), "r"(cta), "r"((int)pred) : "memory");
}
__device__ __forceinline__ void tma_load_3d(uint32_t dst, const CUtensorMap* map, int c0, int c1, int c2, uint32_t bar) {
    asm volatile(
        "cp.async.bulk.tensor.3d.shared::cluster.global.mbarrier::complete_tx::bytes [%0], [%1, {%3, %4, %5}], [%2];"
        ::"r"(dst), "l"(map), "r"(bar), "r"(c0), "r"(c1), "r"(c2) : "memory");
}
__device__ __forceinline__ void tma_load_2d_mc(uint32_t dst, const CUtensorMap* map, int c0, int c1, uint32_t bar, uint16_t mask) {
    asm volatile(
        "cp.async.bulk.tensor.2d.shared::cluster.global.mbarrier::complete_tx::bytes.multicast::cluster [%0], [%1, {%3, %4}], [%2], %5;"
        ::"r"(dst), "l"(map), "r"(bar), "r"(c0), "r"(c1), "h"(mask) : "memory");
}
__device__ __forceinline__ void tma_store_3d(const CUtensorMap* map, uint32_t src, int c0, int c1, int c2) {
    asm volatile("cp.async.bulk.tensor.3d.global.shared::cta.bulk_group [%0, {%2, %3, %4}], [%1];"
                 ::"l"(map), "r"(src), "r"(c0), "r"(c1), "r"(c2) : "memory");
}
__device__ __forceinline__ void wgmma_fence() { asm volatile("wgmma.fence.sync.aligned;" ::: "memory"); }
__device__ __forceinline__ void wgmma_commit() { asm volatile("wgmma.commit_group.sync.aligned;" ::: "memory"); }
template <int N> __device__ __forceinline__ void wgmma_wait() { asm volatile("wgmma.wait_group.sync.aligned %0;" ::"n"(N) : "memory"); }

#define R8(a, i) "+f"(a[i]), "+f"(a[i + 1]), "+f"(a[i + 2]), "+f"(a[i + 3]), "+f"(a[i + 4]), "+f"(a[i + 5]), "+f"(a[i + 6]), "+f"(a[i + 7])
#define R32(a, i) R8(a, i), R8(a, i + 8), R8(a, i + 16), R8(a, i + 24)

__device__ __forceinline__ void wgmma_n256(float (&d)[128], uint64_t da, uint64_t db, int scale_d) {
    asm volatile(
        "{\n.reg .pred p;\nsetp.ne.b32 p, %130, 0;\n"
        "wgmma.mma_async.sync.aligned.m64n256k16.f32.bf16.bf16 "
        "{%0, %1, %2, %3, %4, %5, %6, %7, %8, %9, %10, %11, %12, %13, %14, %15, "
        "%16, %17, %18, %19, %20, %21, %22, %23, %24, %25, %26, %27, %28, %29, %30, %31, "
        "%32, %33, %34, %35, %36, %37, %38, %39, %40, %41, %42, %43, %44, %45, %46, %47, "
        "%48, %49, %50, %51, %52, %53, %54, %55, %56, %57, %58, %59, %60, %61, %62, %63, "
        "%64, %65, %66, %67, %68, %69, %70, %71, %72, %73, %74, %75, %76, %77, %78, %79, "
        "%80, %81, %82, %83, %84, %85, %86, %87, %88, %89, %90, %91, %92, %93, %94, %95, "
        "%96, %97, %98, %99, %100, %101, %102, %103, %104, %105, %106, %107, %108, %109, %110, %111, "
        "%112, %113, %114, %115, %116, %117, %118, %119, %120, %121, %122, %123, %124, %125, %126, %127}, "
        "%128, %129, p, 1, 1, 1, 0;\n}"
        : R32(d, 0), R32(d, 32), R32(d, 64), R32(d, 96)
        : "l"(da), "l"(db), "r"(scale_d));
}
__device__ __forceinline__ void wgmma_n128(float (&d)[64], uint64_t da, uint64_t db, int scale_d) {
    asm volatile(
        "{\n.reg .pred p;\nsetp.ne.b32 p, %66, 0;\n"
        "wgmma.mma_async.sync.aligned.m64n128k16.f32.bf16.bf16 "
        "{%0, %1, %2, %3, %4, %5, %6, %7, %8, %9, %10, %11, %12, %13, %14, %15, "
        "%16, %17, %18, %19, %20, %21, %22, %23, %24, %25, %26, %27, %28, %29, %30, %31, "
        "%32, %33, %34, %35, %36, %37, %38, %39, %40, %41, %42, %43, %44, %45, %46, %47, "
        "%48, %49, %50, %51, %52, %53, %54, %55, %56, %57, %58, %59, %60, %61, %62, %63}, "
        "%64, %65, p, 1, 1, 1, 0;\n}"
        : R32(d, 0), R32(d, 32)
        : "l"(da), "l"(db), "r"(scale_d));
}
__device__ __forceinline__ void wgmma_acc(float (&d)[128], uint64_t da, uint64_t db, int s) { wgmma_n256(d, da, db, s); }
__device__ __forceinline__ void wgmma_acc(float (&d)[64], uint64_t da, uint64_t db, int s) { wgmma_n128(d, da, db, s); }

__device__ __forceinline__ float tanh_fast(float x) {
    float y;
    asm("tanh.approx.f32 %0, %1;" : "=f"(y) : "f"(x));
    return y;
}
__device__ __forceinline__ uint32_t pack_bf16(float lo, float hi) {
    uint32_t r;
    asm("cvt.rn.bf16x2.f32 %0, %1, %2;" : "=r"(r) : "f"(hi), "f"(lo));
    return r;
}

__global__ void __cluster_dims__(2, 1, 1) __launch_bounds__(NTHREADS, 1)
conv_kernel(const __grid_constant__ CUtensorMap mx, const __grid_constant__ CUtensorMap mw,
            const __grid_constant__ CUtensorMap mo) {
    extern __shared__ uint8_t smem_raw[];
    const uint32_t sbase = (smem_u32(smem_raw) + 1023u) & ~1023u;
    uint8_t* sptr = smem_raw + (sbase - smem_u32(smem_raw));
    const uint32_t bar_full = sbase + SM_BAR;
    const uint32_t bar_empty = bar_full + 8 * STAGES;
    const uint32_t bar_xfull = bar_empty + 8 * STAGES;
    const uint32_t bar_xempty = bar_xfull + 16;

    const int warp = __shfl_sync(0xffffffff, threadIdx.x >> 5, 0), lane = threadIdx.x & 31;
    STAMP(0); STAMPG(5);
    const uint32_t rank = blockIdx.x & 1;
    const int cl = blockIdx.x >> 1;
    const int etile = cl & 15;
    const int ttile = ((cl >> 4) << 1) | rank;
    const int bidx = ttile >> 2;
    const int t0 = (ttile & 3) * TILE_T;

    if (threadIdx.x == 0) {
        for (int s = 0; s < STAGES; s++) {
            mbar_init(bar_full + 8 * s, 1);
            mbar_init(bar_empty + 8 * s, 2 * 4 * NWG);
        }
        for (int s = 0; s < 2; s++) {
            mbar_init(bar_xfull + 8 * s, 1);
            mbar_init(bar_xempty + 8 * s, 4 * NWG);
        }
        asm volatile("fence.mbarrier_init.release.cluster;" ::: "memory");
    }
    asm volatile("barrier.cluster.arrive.release.aligned;\nbarrier.cluster.wait.acquire.aligned;" ::: "memory");

    STAMP(1);
    if (warp == NWG * 4) {
        if (lane == 0) {
            int it = 0;
            for (int dc = 0; dc < NCHUNK; dc++) {
                const int xb = dc & 1;
                mbar_wait(bar_xempty + 8 * xb, ((dc >> 1) & 1) ^ 1);
                mbar_expect_tx(bar_xfull + 8 * xb, XBYTES);
                tma_load_3d(sbase + SM_X + xb * XBYTES, &mx, dc * 64, t0 - 28, bidx, bar_xfull + 8 * xb);
                tma_load_3d(sbase + SM_X + xb * XBYTES + 144 * 128, &mx, dc * 64, t0 - 28 + 144, bidx, bar_xfull + 8 * xb);
                for (int tap = 0; tap < KT; tap++, it++) {
                    const int s = it % STAGES;
                    mbar_wait_cluster(bar_empty + 8 * s, ((it / STAGES) & 1) ^ 1);
                    mbar_expect_tx(bar_full + 8 * s, WSTAGE);
                    tma_load_2d_mc(sbase + SM_W + s * WSTAGE + rank * 4096, &mw, rank * 512 + etile * 32,
                                   tap * 512 + dc * 64, bar_full + 8 * s, (uint16_t)3);
                }
            }
        }
    } else {
        const int wg = warp >> 2;
        float acc[NACC];
        const uint64_t descA_hi = ((uint64_t)2 << 62) | ((uint64_t)(512 >> 4) << 32) | ((uint64_t)(4096 >> 4) << 16);
        const uint64_t descB_hi = ((uint64_t)1 << 62) | ((uint64_t)(1024 >> 4) << 32) | ((uint64_t)1 << 16);
        int it = 0;
        for (int dc = 0; dc < NCHUNK; dc++) {
            const int xb = dc & 1;
            mbar_wait(bar_xfull + 8 * xb, (dc >> 1) & 1);
            const uint32_t xaddr = sbase + SM_X + xb * XBYTES + wg * (NCOLS * 128);
            for (int tap = 0; tap < KT; tap++, it++) {
                const int s = it % STAGES;
                mbar_wait(bar_full + 8 * s, (it / STAGES) & 1);
                if (it == 0) STAMP(2);
                const uint32_t waddr = sbase + SM_W + s * WSTAGE;
                const uint64_t da = descA_hi | (uint64_t)((waddr & 0x3FFFF) >> 4);
                const uint64_t db = descB_hi | (uint64_t)(((xaddr + tap * 256) & 0x3FFFF) >> 4);
                wgmma_fence();
#pragma unroll
                for (int k = 0; k < 4; k++) wgmma_acc(acc, da + k * (1024 >> 4), db + k * (32 >> 4), (it | k) != 0);
                wgmma_commit();
                wgmma_wait<1>();
                {
                    const int pit = it - 1;
                    const int ps = (pit + STAGES) % STAGES;
                    mbar_arrive_cluster_pred(bar_empty + 8 * ps, lane & 1, lane < 2 && pit >= 0 && pit < NITER - STAGES);
                    mbar_arrive_pred(bar_xempty + 8 * (xb ^ 1), tap == 0 && it > 0 && lane == 0);
                }
            }
        }
        wgmma_wait<0>();
        STAMP(3);

        asm volatile("bar.sync 1, %0;" ::"n"(NWG * 128) : "memory");
        const int w4 = warp & 3;
        const bool is_f = w4 < 2;
        constexpr int HALF = NACC / 2;
        if (is_f) {
#pragma unroll
            for (int i = 0; i < NACC; i++) acc[i] = tanh_fast(acc[i]);
        } else {
#pragma unroll
            for (int i = 0; i < NACC; i++) acc[i] = fmaf(tanh_fast(0.5f * acc[i]), 0.5f, 0.5f);
        }
        float4* ex = reinterpret_cast<float4*>(sptr + SM_X) + (wg * 4) * (HALF / 4) * 32;
        {
            float4* mine = ex + w4 * (HALF / 4) * 32 + lane;
#pragma unroll
            for (int i = 0; i < HALF / 4; i++) {
                if (is_f) mine[i * 32] = make_float4(acc[HALF + 4 * i], acc[HALF + 4 * i + 1], acc[HALF + 4 * i + 2], acc[HALF + 4 * i + 3]);
                else mine[i * 32] = make_float4(acc[4 * i], acc[4 * i + 1], acc[4 * i + 2], acc[4 * i + 3]);
            }
        }
        asm volatile("bar.sync %0, 128;" ::"r"(2 + wg) : "memory");
        uint32_t pk[HALF / 2];
        {
            const float4* other = ex + (w4 ^ 2) * (HALF / 4) * 32 + lane;
#pragma unroll
            for (int i = 0; i < HALF / 4; i++) {
                float4 o = other[i * 32];
                float a0, a1, a2, a3;
                if (is_f) { a0 = acc[4 * i]; a1 = acc[4 * i + 1]; a2 = acc[4 * i + 2]; a3 = acc[4 * i + 3]; }
                else { a0 = acc[HALF + 4 * i]; a1 = acc[HALF + 4 * i + 1]; a2 = acc[HALF + 4 * i + 2]; a3 = acc[HALF + 4 * i + 3]; }
                pk[2 * i] = pack_bf16(a0 * o.x, a1 * o.y);
                pk[2 * i + 1] = pack_bf16(a2 * o.z, a3 * o.w);
            }
        }
        const uint32_t stg = sbase + SM_X + 32768 + wg * (NCOLS * 64);
        {
            const int mi = lane >> 3, r = lane & 7;
            const int jbase = is_f ? 0 : (NCOLS / 16);
            const int chunk = (w4 & 1) * 2 + (mi & 1);
#pragma unroll
            for (int i = 0; i < HALF / 8; i++) {
                const int trow = (jbase + 2 * i + (mi >> 1)) * 8 + r;
                const uint32_t addr = stg + trow * 64 + ((chunk ^ ((trow >> 1) & 3)) << 4);
                asm volatile("stmatrix.sync.aligned.m8n8.x4.trans.shared.b16 [%0], {%1, %2, %3, %4};"
                             ::"r"(addr), "r"(pk[4 * i]), "r"(pk[4 * i + 1]), "r"(pk[4 * i + 2]), "r"(pk[4 * i + 3]) : "memory");
            }
        }
        asm volatile("fence.proxy.async.shared::cta;" ::: "memory");
        asm volatile("bar.sync %0, 128;" ::"r"(2 + wg) : "memory");
        if ((threadIdx.x & 127) == 0) {
            tma_store_3d(&mo, stg, etile * 32, t0 + wg * NCOLS, bidx);
            asm volatile("cp.async.bulk.commit_group;" ::: "memory");
            asm volatile("cp.async.bulk.wait_group.read 0;" ::: "memory");
            STAMP(4); STAMPG(6);
        }
    }
}

typedef CUresult (*EncodeFn)(CUtensorMap*, CUtensorMapDataType, cuuint32_t, void*, const cuuint64_t*, const cuuint64_t*,
                             const cuuint32_t*, const cuuint32_t*, CUtensorMapInterleave, CUtensorMapSwizzle,
                             CUtensorMapL2promotion, CUtensorMapFloatOOBfill);

}

extern "C" void kernel_launch(void* const* d_in, const int* in_sizes, int n_in, void* d_out, int out_size) {
    static EncodeFn enc = nullptr;
    if (!enc) {
        void* fn = nullptr;
        cudaDriverEntryPointQueryResult qres;
        cudaGetDriverEntryPoint("cuTensorMapEncodeTiled", &fn, cudaEnableDefault, &qres);
        enc = (EncodeFn)fn;
        cudaFuncSetAttribute(conv_kernel, cudaFuncAttributeMaxDynamicSharedMemorySize, SM_TOTAL);
    }
    CUtensorMap mx, mw, mo;
    {
        cuuint64_t dims[3] = {(cuuint64_t)D_, (cuuint64_t)T_, 2};
        cuuint64_t strides[2] = {(cuuint64_t)D_ * 2, (cuuint64_t)D_ * 2 * T_};
        cuuint32_t box[3] = {64, 144, 1};
        cuuint32_t es[3] = {1, 1, 1};
        enc(&mx, CU_TENSOR_MAP_DATA_TYPE_BFLOAT16, 3, d_in[0], dims, strides, box, es, CU_TENSOR_MAP_INTERLEAVE_NONE,
            CU_TENSOR_MAP_SWIZZLE_128B, CU_TENSOR_MAP_L2_PROMOTION_L2_128B, CU_TENSOR_MAP_FLOAT_OOB_FILL_NONE);
    }
    {
        cuuint64_t dims[2] = {1024, (cuuint64_t)KT * D_};
        cuuint64_t strides[1] = {2048};
        cuuint32_t box[2] = {32, 64};
        cuuint32_t es[2] = {1, 1};
        enc(&mw, CU_TENSOR_MAP_DATA_TYPE_BFLOAT16, 2, d_in[1], dims, strides, box, es, CU_TENSOR_MAP_INTERLEAVE_NONE,
            CU_TENSOR_MAP_SWIZZLE_64B, CU_TENSOR_MAP_L2_PROMOTION_L2_128B, CU_TENSOR_MAP_FLOAT_OOB_FILL_NONE);
    }
    {
        cuuint64_t dims[3] = {(cuuint64_t)D_, (cuuint64_t)T_, 2};
        cuuint64_t strides[2] = {(cuuint64_t)D_ * 2, (cuuint64_t)D_ * 2 * T_};
        cuuint32_t box[3] = {32, (cuuint32_t)NCOLS, 1};
        cuuint32_t es[3] = {1, 1, 1};
        enc(&mo, CU_TENSOR_MAP_DATA_TYPE_BFLOAT16, 3, d_out, dims, strides, box, es, CU_TENSOR_MAP_INTERLEAVE_NONE,
            CU_TENSOR_MAP_SWIZZLE_64B, CU_TENSOR_MAP_L2_PROMOTION_NONE, CU_TENSOR_MAP_FLOAT_OOB_FILL_NONE);
    }
    conv_kernel<<<128, NTHREADS, SM_TOTAL>>>(mx, mw, mo);
}
```

```cpp
#include <cuda_runtime.h>
#include <cuda_bf16.h>
#include <cuda.h>
#include <stdint.h>

namespace {

constexpr int T_ = 1000, D_ = 512;
constexpr int VROWS = 92;
constexpr int VTILE = VROWS * 128;
constexpr int VBYTES = 5 * VTILE;
constexpr int VBUF = 59392;
constexpr int WSTAGE = 24576;
constexpr int NST = 4;
constexpr int NUNIT = 40;
constexpr int SM_V = 0;
constexpr int SM_W = 2 * VBUF;
constexpr int SM_BAR = SM_W + NST * WSTAGE;
constexpr int SM_TOTAL = SM_BAR + 512 + 1024;
constexpr int NTHREADS = 384;
constexpr int NEARLY = 2;
constexpr int PFD = 6;
constexpr int GOFREE = 3;

__device__ __nv_bfloat16 g_V[8 * 5 * VROWS * D_];
__device__ unsigned int g_flag[8 * 32];

__device__ __forceinline__ uint32_t smem_u32(const void* p) { return (uint32_t)__cvta_generic_to_shared(p); }
__device__ __forceinline__ void mbar_init(uint32_t bar, uint32_t cnt) {
    asm volatile("mbarrier.init.shared::cta.b64 [%0], %1;" ::"r"(bar), "r"(cnt) : "memory");
}
__device__ __forceinline__ void mbar_expect_tx(uint32_t bar, uint32_t bytes) {
    asm volatile("mbarrier.arrive.expect_tx.shared::cta.b64 _, [%0], %1;" ::"r"(bar), "r"(bytes) : "memory");
}
__device__ __forceinline__ void mbar_wait(uint32_t bar, uint32_t parity) {
    asm volatile(
        "{\n.reg .pred p;\n.reg .b32 n;\n"
        "mov.b32 n, 0;\n"
        "LAB_WAIT:\n"
        "mbarrier.try_wait.parity.shared::cta.b64 p, [%0], %1;\n"
        "@p bra LAB_DONE;\n"
        "add.u32 n, n, 1;\n"
        "setp.lt.u32 p, n, 0x400000;\n"
        "@p bra LAB_WAIT;\n"
        "trap;\n"
        "LAB_DONE:\n}" ::"r"(bar), "r"(parity) : "memory");
}
__device__ __forceinline__ void mbar_arrive_pred(uint32_t bar, bool pred) {
    asm volatile("{\n.reg .pred p;\nsetp.ne.b32 p, %1, 0;\n@p mbarrier.arrive.shared::cta.b64 _, [%0];\n}" ::"r"(bar), "r"((int)pred) : "memory");
}
__device__ __forceinline__ uint32_t mbar_try(uint32_t bar, uint32_t parity) {
    uint32_t ok;
    asm volatile("{\n.reg .pred p;\nmbarrier.try_wait.parity.shared::cta.b64 p, [%1], %2;\nselp.b32 %0, 1, 0, p;\n}"
                 : "=r"(ok) : "r"(bar), "r"(parity) : "memory");
    return ok;
}
__device__ __forceinline__ uint32_t mapa(uint32_t addr, uint32_t cta) {
    uint32_t r;
    asm("mapa.shared::cluster.u32 %0, %1, %2;" : "=r"(r) : "r"(addr), "r"(cta));
    return r;
}
__device__ __forceinline__ void mbar_arrive_remote_pred(uint32_t raddr, bool pred) {
    asm volatile("{\n.reg .pred p;\nsetp.ne.b32 p, %1, 0;\n@p mbarrier.arrive.shared::cluster.b64 _, [%0];\n}" ::"r"(raddr), "r"((int)pred) : "memory");
}
__device__ __forceinline__ uint64_t mk_desc(uint32_t lo, uint32_t hi) {
    return ((uint64_t)hi << 32) | (uint64_t)lo;
}
__device__ __forceinline__ void tma_load_4d(uint32_t dst, const CUtensorMap* map, int c0, int c1, int c2, int c3, uint32_t bar) {
    asm volatile(
        "cp.async.bulk.tensor.4d.shared::cluster.global.mbarrier::complete_tx::bytes [%0], [%1, {%3, %4, %5, %6}], [%2];"
        ::"r"(dst), "l"(map), "r"(bar), "r"(c0), "r"(c1), "r"(c2), "r"(c3) : "memory");
}
__device__ __forceinline__ void tma_load_3d(uint32_t dst, const CUtensorMap* map, int c0, int c1, int c2, uint32_t bar) {
    asm volatile(
        "cp.async.bulk.tensor.3d.shared::cluster.global.mbarrier::complete_tx::bytes [%0], [%1, {%3, %4, %5}], [%2];"
        ::"r"(dst), "l"(map), "r"(bar), "r"(c0), "r"(c1), "r"(c2) : "memory");
}
__device__ __forceinline__ void tma_load_3d_mc(uint32_t dst, const CUtensorMap* map, int c0, int c1, int c2, uint32_t bar, uint16_t mask) {
    asm volatile(
        "cp.async.bulk.tensor.3d.shared::cluster.global.mbarrier::complete_tx::bytes.multicast::cluster [%0], [%1, {%3, %4, %5}], [%2], %6;"
        ::"r"(dst), "l"(map), "r"(bar), "r"(c0), "r"(c1), "r"(c2), "h"(mask) : "memory");
}
__device__ __forceinline__ void wgmma_fence() { asm volatile("wgmma.fence.sync.aligned;" ::: "memory"); }
__device__ __forceinline__ void wgmma_commit() { asm volatile("wgmma.commit_group.sync.aligned;" ::: "memory"); }
template <int N> __device__ __forceinline__ void wgmma_wait() { asm volatile("wgmma.wait_group.sync.aligned %0;" ::"n"(N) : "memory"); }
__device__ __forceinline__ void ldsm_x4_t(uint32_t (&r)[4], uint32_t addr) {
    asm volatile("ldmatrix.sync.aligned.m8n8.x4.trans.shared.b16 {%0,%1,%2,%3}, [%4];"
                 : "=r"(r[0]), "=r"(r[1]), "=r"(r[2]), "=r"(r[3]) : "r"(addr) : "memory");
}
__device__ __forceinline__ void stsm_x4_t(uint32_t addr, uint32_t a, uint32_t b, uint32_t c, uint32_t d) {
    asm volatile("stmatrix.sync.aligned.m8n8.x4.trans.shared.b16 [%0], {%1, %2, %3, %4};" ::"r"(addr), "r"(a), "r"(b), "r"(c), "r"(d) : "memory");
}
template <int TA> __device__ __forceinline__ void wgmma_ss_88(float (&d)[44], uint64_t da, uint64_t db, int sd) {
    asm volatile("{\n.reg .pred p;\nsetp.ne.b32 p, %46, 0;\n"
        "wgmma.mma_async.sync.aligned.m64n88k16.f32.bf16.bf16 {%0, %1, %2, %3, %4, %5, %6, %7, %8, %9, %10, %11, %12, %13, %14, %15, %16, %17, %18, %19, %20, %21, %22, %23, %24, %25, %26, %27, %28, %29, %30, %31, %32, %33, %34, %35, %36, %37, %38, %39, %40, %41, %42, %43}, %44, %45, p, 1, 1, %47, 0;\n}"
        : "+f"(d[0]), "+f"(d[1]), "+f"(d[2]), "+f"(d[3]), "+f"(d[4]), "+f"(d[5]), "+f"(d[6]), "+f"(d[7]), "+f"(d[8]), "+f"(d[9]), "+f"(d[10]), "+f"(d[11]), "+f"(d[12]), "+f"(d[13]), "+f"(d[14]), "+f"(d[15]), "+f"(d[16]), "+f"(d[17]), "+f"(d[18]), "+f"(d[19]), "+f"(d[20]), "+f"(d[21]), "+f"(d[22]), "+f"(d[23]), "+f"(d[24]), "+f"(d[25]), "+f"(d[26]), "+f"(d[27]), "+f"(d[28]), "+f"(d[29]), "+f"(d[30]), "+f"(d[31]), "+f"(d[32]), "+f"(d[33]), "+f"(d[34]), "+f"(d[35]), "+f"(d[36]), "+f"(d[37]), "+f"(d[38]), "+f"(d[39]), "+f"(d[40]), "+f"(d[41]), "+f"(d[42]), "+f"(d[43]) : "l"(da), "l"(db), "r"(sd), "n"(TA));
}
__device__ __forceinline__ void wgmma_rs_88(float (&d)[44], const uint32_t (&a)[4], uint64_t db, int sd) {
    asm volatile("{\n.reg .pred p;\nsetp.ne.b32 p, %49, 0;\n"
        "wgmma.mma_async.sync.aligned.m64n88k16.f32.bf16.bf16 {%0, %1, %2, %3, %4, %5, %6, %7, %8, %9, %10, %11, %12, %13, %14, %15, %16, %17, %18, %19, %20, %21, %22, %23, %24, %25, %26, %27, %28, %29, %30, %31, %32, %33, %34, %35, %36, %37, %38, %39, %40, %41, %42, %43}, {%44, %45, %46, %47}, %48, p, 1, 1, 0;\n}"
        : "+f"(d[0]), "+f"(d[1]), "+f"(d[2]), "+f"(d[3]), "+f"(d[4]), "+f"(d[5]), "+f"(d[6]), "+f"(d[7]), "+f"(d[8]), "+f"(d[9]), "+f"(d[10]), "+f"(d[11]), "+f"(d[12]), "+f"(d[13]), "+f"(d[14]), "+f"(d[15]), "+f"(d[16]), "+f"(d[17]), "+f"(d[18]), "+f"(d[19]), "+f"(d[20]), "+f"(d[21]), "+f"(d[22]), "+f"(d[23]), "+f"(d[24]), "+f"(d[25]), "+f"(d[26]), "+f"(d[27]), "+f"(d[28]), "+f"(d[29]), "+f"(d[30]), "+f"(d[31]), "+f"(d[32]), "+f"(d[33]), "+f"(d[34]), "+f"(d[35]), "+f"(d[36]), "+f"(d[37]), "+f"(d[38]), "+f"(d[39]), "+f"(d[40]), "+f"(d[41]), "+f"(d[42]), "+f"(d[43]) : "r"(a[0]), "r"(a[1]), "r"(a[2]), "r"(a[3]), "l"(db), "r"(sd));
}


__device__ __forceinline__ float tanh_fast(float x) {
    float y;
    asm("tanh.approx.f32 %0, %1;" : "=f"(y) : "f"(x));
    return y;
}
__device__ __forceinline__ uint32_t pack_bf16(float lo, float hi) {
    uint32_t r;
    asm("cvt.rn.bf16x2.f32 %0, %1, %2;" : "=r"(r) : "f"(hi), "f"(lo));
    return r;
}
__device__ __forceinline__ uint32_t hfma2(uint32_t a, uint32_t b, uint32_t c) {
    uint32_t d;
    asm("fma.rn.bf16x2 %0, %1, %2, %3;" : "=r"(d) : "r"(a), "r"(b), "r"(c));
    return d;
}
constexpr uint32_t BF_ONE = 0x3f803f80u, BF_MHALF = 0xbf00bf00u;
__device__ __forceinline__ float bf_lo(uint32_t v) { return __uint_as_float(v << 16); }
__device__ __forceinline__ float bf_hi(uint32_t v) { return __uint_as_float(v & 0xffff0000u); }

__device__ __forceinline__ void vtrans(const uint4& d0, const uint4& d1, const uint4& d2, const uint4& d3, const uint4& d4, uint4 (&o)[5]) {
#pragma unroll
    for (int j = 0; j < 4; j++) {
        float v[5][2];
#pragma unroll
        for (int h = 0; h < 2; h++) {
            const uint32_t w0 = (&d0.x)[j], w1 = (&d1.x)[j], w2 = (&d2.x)[j], w3 = (&d3.x)[j], w4 = (&d4.x)[j];
            const float e0 = h ? bf_hi(w0) : bf_lo(w0), e1 = h ? bf_hi(w1) : bf_lo(w1), e2 = h ? bf_hi(w2) : bf_lo(w2);
            const float e3 = h ? bf_hi(w3) : bf_lo(w3), e4 = h ? bf_hi(w4) : bf_lo(w4);
            v[0][h] = fmaf(e2 - e1, 1.5f, e3 - e0);
            v[1][h] = fmaf(e2, 2.5f, e1 + e3);
            v[2][h] = fmaf(e1, -2.f, e2 + e3);
            v[3][h] = fmaf(e1 + e2, -0.5f, e3);
            v[4][h] = fmaf(e3 - e2, 1.5f, e4 - e1);
        }
#pragma unroll
        for (int i = 0; i < 5; i++) (&o[i].x)[j] = pack_bf16(v[i][0], v[i][1]);
    }
}
__device__ __forceinline__ void load_rows(uint4 (&d)[11], const char* base, int tb) {
#pragma unroll
    for (int k = 0; k < 11; k++) {
        asm volatile(
            "{\n.reg .pred p;\nsetp.lt.u32 p, %5, 1000;\n"
            "mov.b32 %0, 0;\nmov.b32 %1, 0;\nmov.b32 %2, 0;\nmov.b32 %3, 0;\n"
            "@p ld.global.nc.v4.u32 {%0, %1, %2, %3}, [%4];\n}"
            : "=r"(d[k].x), "=r"(d[k].y), "=r"(d[k].z), "=r"(d[k].w) : "l"(base + k * 2048), "r"(tb + 2 * k));
    }
}
__device__ __forceinline__ bool elect_one() {
    uint32_t pred;
    asm volatile("{\n.reg .pred p;\nelect.sync _|p, 0xffffffff;\nselp.b32 %0, 1, 0, p;\n}" : "=r"(pred));
    return pred != 0;
}

__device__ __forceinline__ void wtransform(const uint32_t (&g0)[4], const uint32_t (&r)[2][4], uint32_t (&t)[3][4]) {
#pragma unroll
    for (int j = 0; j < 4; j++) {
        t[0][j] = hfma2(hfma2(g0[j], BF_ONE, r[1][j]), BF_ONE, r[0][j]);
        t[1][j] = hfma2(hfma2(r[1][j], BF_MHALF, r[0][j]), BF_MHALF, g0[j]);
        t[2][j] = hfma2(hfma2(g0[j], BF_MHALF, r[0][j]), BF_MHALF, r[1][j]);
    }
}

__device__ __forceinline__ void stsm_x2_t(uint32_t addr, uint32_t a, uint32_t b) {
    asm volatile("stmatrix.sync.aligned.m8n8.x2.trans.shared.b16 [%0], {%1, %2};" ::"r"(addr), "r"(a), "r"(b) : "memory");
}
constexpr float I1 = 1.f / 4.5f, I2 = 1.f / 1.125f, I3 = -4.f / 9.f;
__device__ __forceinline__ void otrans01(const float* m0, const float* m1, const float* m2, const float* m3, float* y0, float* y1, float* z2) {
#pragma unroll
    for (int q = 0; q < 4; q++) {
        const float h = q < 2 ? 1.f : 0.5f;
        const float a = m1[q] * (I1 * h);
        y0[q] = fmaf(m3[q], I3 * h, fmaf(m2[q], I2 * h, fmaf(m0[q], -h, a)));
        y1[q] = fmaf(m3[q], -2.f * I3 * h, fmaf(m2[q], -0.5f * I2 * h, a));
        z2[q] = fmaf(m3[q], 4.f * I3 * h, fmaf(m2[q], 0.25f * I2 * h, a));
    }
}
__device__ __forceinline__ uint32_t gate(const float* y) {
    return pack_bf16(tanh_fast(y[0]) * fmaf(tanh_fast(y[2]), 0.5f, 0.5f), tanh_fast(y[1]) * fmaf(tanh_fast(y[3]), 0.5f, 0.5f));
}
__device__ __forceinline__ void stage48(const uint32_t (&pk)[6], uint32_t slab, int o, int lane, int w4) {
    const uint32_t a = slab + (48 * o + lane) * 64 + ((w4 ^ ((lane >> 1) & 3)) << 4);
    stsm_x4_t(a, pk[0], pk[1], pk[2], pk[3]);
    stsm_x2_t(a + 32 * 64, pk[4], pk[5]);
}
template <int BAR>
__device__ __forceinline__ void finish(const uint32_t (&pk)[3][6], uint32_t slab, char* gout, int tlim, int nbase, int tid) {
    const int lane = tid & 31, w4 = tid >> 5;
    const int q = tid >> 2, ch = tid & 3;
    uint32_t sa[5];
    int toff[5];
#pragma unroll
    for (int r = 0; r < 5; r++) {
        const int R = (r < 4 ? 32 * r : 112) + q;
        const int o = (R >= 48) + (R >= 96), n = nbase + R - 48 * o;
        const int t = 6 * (n >> 1) + (n & 1) + 2 * o;
        sa[r] = slab + R * 64 + ((ch ^ ((R >> 1) & 3)) << 4);
        toff[r] = (n < 84 && t < tlim && (r < 4 || q >= 16)) ? t * (D_ * 2) + ch * 16 : -1;
    }
#pragma unroll
    for (int o = 0; o < 3; o++) stage48(pk[o], slab, o, lane, w4);
    asm volatile("bar.sync %0, 128;" ::"n"(BAR) : "memory");
    uint4 v[5];
#pragma unroll
    for (int r = 0; r < 5; r++)
        asm volatile("ld.shared.v4.u32 {%0,%1,%2,%3}, [%4];" : "=r"(v[r].x), "=r"(v[r].y), "=r"(v[r].z), "=r"(v[r].w) : "r"(sa[r]) : "memory");
#pragma unroll
    for (int r = 0; r < 5; r++)
        asm volatile("{\n.reg .pred p;\nsetp.ge.s32 p, %5, 0;\n@p st.global.v4.u32 [%0], {%1, %2, %3, %4};\n}"
                     ::"l"(gout + toff[r]), "r"(v[r].x), "r"(v[r].y), "r"(v[r].z), "r"(v[r].w), "r"(toff[r]) : "memory");
}

__global__ void __cluster_dims__(2, 1, 1) __launch_bounds__(NTHREADS, 1)
conv_kernel(const __grid_constant__ CUtensorMap mv, const __grid_constant__ CUtensorMap mw,
            const __nv_bfloat16* __restrict__ x, __nv_bfloat16* __restrict__ out) {
    extern __shared__ uint8_t smem_raw[];
    const uint32_t sbase = (smem_u32(smem_raw) + 1023u) & ~1023u;
    uint8_t* sptr = smem_raw + (sbase - smem_u32(smem_raw));
    const uint32_t bar_full = sbase + SM_BAR;
    const uint32_t bar_empty = bar_full + 8 * NST;
    const uint32_t bar_vfull = bar_empty + 8 * NST;
    const uint32_t bar_vempty = bar_vfull + 16;
    const uint32_t bar_go = bar_vempty + 16;

    const int warp = __shfl_sync(0xffffffff, threadIdx.x >> 5, 0), lane = threadIdx.x & 31;
    const uint32_t rank = blockIdx.x & 1;
    const int cl = blockIdx.x >> 1;
    const int etile = cl & 15;
    const int ttile = ((cl >> 4) << 1) | rank;
    const int bidx = ttile >> 2;
    const int tt = ttile & 3;

    const bool loc = warp < 8;
    const int vec = loc ? (threadIdx.x & 7) : min(8 + ((threadIdx.x - 256) >> 1), 63);
    const int par = loc ? ((threadIdx.x >> 3) & 1) : (threadIdx.x & 1);
    const int a0 = 3 * (loc ? (threadIdx.x >> 4) : etile);
    const int tb = 252 * tt + 6 * a0 - 28 + par;
    const char* xrow = reinterpret_cast<const char*>(x) + (long long)(bidx * T_ + tb) * (D_ * 2) + vec * 16;
    uint4 d[11];
    if (warp == 8) {
        load_rows(d, xrow, tb);
        if (elect_one()) {
            asm volatile("prefetch.tensormap [%0];" ::"l"(&mw) : "memory");
            for (int s = 0; s < NST; s++) {
                mbar_init(bar_full + 8 * s, 1);
                mbar_init(bar_empty + 8 * s, 16);
            }
            for (int s = 0; s < NST * 4; s++) mbar_init(bar_go + 8 * s, 1);
            for (int s = 0; s < 2; s++) {
                mbar_init(bar_vfull + 8 * s, 1);
                mbar_init(bar_vempty + 8 * s, 8);
            }
            asm volatile("fence.mbarrier_init.release.cluster;" ::: "memory");
            for (int u = 0; u < NEARLY; u++) {
                mbar_expect_tx(bar_full + 8 * u, WSTAGE);
                tma_load_3d(sbase + SM_W + u * WSTAGE, &mw, etile * 32, 0, 3 * u, bar_full + 8 * u);
                tma_load_3d(sbase + SM_W + u * WSTAGE + 12288, &mw, 512 + etile * 32, 0, 3 * u, bar_full + 8 * u);
            }
            asm volatile("prefetch.tensormap [%0];" ::"l"(&mv) : "memory");
        }
        __syncwarp();
    } else {
        load_rows(d, xrow, tb);
    }
    asm volatile("barrier.cluster.arrive.relaxed.aligned;" ::: "memory");
    {
        uint8_t* dst = loc ? sptr + SM_V : reinterpret_cast<uint8_t*>(g_V) + (size_t)ttile * (5 * VROWS * D_ * 2);
        const int pitch = loc ? 128 : 1024, swz = loc ? 7 : 0;
#pragma unroll
        for (int a = 0; a < 3; a++) {
            uint4 o[5];
            vtrans(d[3 * a], d[3 * a + 1], d[3 * a + 2], d[3 * a + 3], d[3 * a + 4], o);
            const int rho = 2 * (a0 + a) + par;
            if (rho < VROWS) {
#pragma unroll
                for (int i = 0; i < 5; i++) {
                    const int row = i * VROWS + rho;
                    *reinterpret_cast<uint4*>(dst + row * pitch + ((vec ^ (row & swz)) << 4)) = o[i];
                }
            }
        }
    }

    constexpr uint32_t DA_HI = (2u << 30) | (512u >> 4), DA_LO = (12288u >> 4) << 16;
    constexpr uint32_t DB_HI = (1u << 30) | (1024u >> 4), DB_LO = 1u << 16;
    const uint32_t vlo0 = DB_LO | (((sbase + SM_V) & 0x3FFFF) >> 4);
    const uint32_t rem_empty = mapa(bar_empty, lane & 1);
    const int w4 = warp & 3;
    const uint32_t slab = sbase;
    float4* ex_acc = reinterpret_cast<float4*>(sptr + 18432);
    char* gout = reinterpret_cast<char*>(out) + ((size_t)(bidx * T_ + tt * 252) * D_ + etile * 32) * 2;
    const int tlim = min(252, T_ - tt * 252);
    float2* ex_m4 = reinterpret_cast<float2*>(sptr + SM_W + WSTAGE);

    if (warp >= 8) {
        asm volatile("bar.sync 4, 128;" ::: "memory");
        if (threadIdx.x == 320) asm volatile("red.release.gpu.global.add.u32 [%0], 1;" ::"l"(&g_flag[ttile * 32]) : "memory");
        asm volatile("barrier.cluster.wait.aligned;" ::: "memory");
        if (warp == 8) { if (elect_one()) {
            int c = 0, g = NEARLY;
            for (int u = NEARLY; u < NUNIT; u++) {
                const int s = u & (NST - 1);
                mbar_wait(bar_empty + 8 * s, ((u / NST) & 1) ^ 1);
                mbar_expect_tx(bar_full + 8 * s, WSTAGE);
                tma_load_3d_mc(sbase + SM_W + s * WSTAGE + rank * 12288, &mw, rank * 512 + etile * 32, c * 64, 3 * g,
                               bar_full + 8 * s, (uint16_t)3);
                if (++g == 5) { g = 0; c++; }
                const int up = u + PFD;
                if (up < NUNIT && (up & 3) == (cl >> 4))
                    asm volatile("cp.async.bulk.prefetch.tensor.3d.L2.global [%0, {%1, %2, %3}];"
                                 ::"l"(&mw), "r"((int)(rank * 512 + etile * 32)), "r"((up / 5) * 64), "r"(3 * (up % 5)) : "memory");
            } }
        } else if (warp == 9) { if (elect_one()) {
            unsigned int* flag = &g_flag[ttile * 32];
            unsigned int v, n = 0;
            do {
                asm volatile("ld.acquire.gpu.global.u32 %0, [%1];" : "=r"(v) : "l"(flag) : "memory");
                if (++n > (1u << 22)) __trap();
            } while (v < 16);
            asm volatile("fence.proxy.async.global;" ::: "memory");
            for (int c = 1; c < 8; c++) {
                const int vb = c & 1;
                mbar_wait(bar_vempty + 8 * vb, ((c >> 1) & 1) ^ 1);
                mbar_expect_tx(bar_vfull + 8 * vb, VBYTES);
                tma_load_4d(sbase + SM_V + vb * VBUF, &mv, c * 64, 0, 0, ttile, bar_vfull + 8 * vb);
                if (c == 1) {
                    if (atomicAdd(flag + 1, 1u) == 15u) { flag[1] = 0; __threadfence(); atomicExch(flag, 0u); }
                }
            } }
        }
    } else if (warp >= 4) {
        asm volatile("fence.proxy.async.shared::cta;" ::: "memory");
        asm volatile("setmaxnreg.dec.sync.aligned.u32 88;");
        asm volatile("bar.sync 1, 256;" ::: "memory");
        asm volatile("barrier.cluster.wait.aligned;" ::: "memory");
        float m4[44];
        int c = 0, g = 0;
        const uint64_t da = mk_desc(DA_LO | (((sbase + SM_W + 8192) & 0x3FFFF) >> 4), DA_HI);
        for (int it = 0; it < NUNIT / NST; it++) {
#pragma unroll
            for (int s = 0; s < NST; s++) {
                if (g == 0) mbar_wait(bar_vfull + 8 * (c & 1), (c >> 1) & 1);
                mbar_wait(bar_full + 8 * s, it & 1);
                const uint64_t db = mk_desc(vlo0 + (c & 1) * (VBUF >> 4) + g * 16 + ((4 * VTILE) >> 4), DB_HI);
#pragma unroll
                for (int kk = 0; kk < 4; kk++) {
                    if (it < NUNIT / NST - 1 || s < GOFREE) mbar_wait(bar_go + 8 * (s * 4 + kk), it & 1);
                    wgmma_fence();
                    wgmma_ss_88<1>(m4, da + ((s * WSTAGE + kk * 1024) >> 4), db + kk * 2, (s + kk > 0) ? 1 : it);
                    wgmma_commit();
                    if (kk == 0) {
                        wgmma_wait<1>();
                        mbar_arrive_remote_pred(rem_empty + 8 * ((s + NST - 1) & (NST - 1)), lane < 2 && (s > 0 ? it < NUNIT / NST - 1 : it > 0));
                        mbar_arrive_pred(bar_vempty + 8 * ((c & 1) ^ 1), g == 0 && c > 0 && lane == 0);
                    }
                }
                if (++g == 5) { g = 0; c++; }
            }
        }
        wgmma_wait<0>();
        {
            const int slot = w4 >> 1, wa = (w4 & 1) * 2;
#pragma unroll
            for (int j = 0; j < 11; j++) {
                ex_m4[((wa * 2 + slot) * 11 + j) * 32 + lane] = make_float2(m4[4 * j], m4[4 * j + 1]);
                ex_m4[(((wa + 1) * 2 + slot) * 11 + j) * 32 + lane] = make_float2(m4[4 * j + 2], m4[4 * j + 3]);
            }
        }
        asm volatile("bar.arrive 5, 256;" ::: "memory");
        asm volatile("bar.sync 1, 256;" ::: "memory");
        uint32_t pk[3][6];
        pk[0][5] = pk[1][5] = pk[2][5] = 0;
#pragma unroll
        for (int j = 0; j < 5; j++) {
            float4 a[4];
#pragma unroll
            for (int k = 0; k < 4; k++) a[k] = ex_acc[((k * 4 + w4) * 5 + j) * 32 + lane];
            const float2 f = ex_m4[((w4 * 2 + 0) * 11 + 6 + j) * 32 + lane];
            const float2 gg = ex_m4[((w4 * 2 + 1) * 11 + 6 + j) * 32 + lane];
            float y0[4], y1[4], y2[4];
            otrans01(&a[0].x, &a[1].x, &a[2].x, &a[3].x, y0, y1, y2);
            y2[0] += f.x; y2[1] += f.y; y2[2] = fmaf(gg.x, 0.5f, y2[2]); y2[3] = fmaf(gg.y, 0.5f, y2[3]);
            pk[0][j] = gate(y0); pk[1][j] = gate(y1); pk[2][j] = gate(y2);
        }
        finish<3>(pk, slab + 9216, gout, tlim, 48, threadIdx.x - 128);
    } else {
        asm volatile("fence.proxy.async.shared::cta;" ::: "memory");
        asm volatile("setmaxnreg.inc.sync.aligned.u32 248;");
        asm volatile("bar.sync 1, 256;" ::: "memory");
        asm volatile("barrier.cluster.wait.aligned;" ::: "memory");
        mbar_arrive_pred(bar_vfull, threadIdx.x == 0);
        float m0[44], m1[44], m2[44], m3[44];
        uint32_t g0[4][4], raw[2][2][4], tr[2][3][4];
        const int krow = (lane & 7) + ((lane >> 4) << 3);
        const uint32_t lds_off = sbase + SM_W + ((lane >> 3) & 1) * 12288 + krow * 64 + ((w4 ^ ((krow >> 1) & 3)) << 4);
        mbar_wait(bar_full, 0);
#pragma unroll
        for (int q = 0; q < 2; q++) {
            ldsm_x4_t(g0[q], lds_off + q * 1024);
            ldsm_x4_t(raw[q][0], lds_off + 4096 + q * 1024);
            ldsm_x4_t(raw[q][1], lds_off + 8192 + q * 1024);
        }
        int c = 0, g = 0;
        for (int it = 0; it < NUNIT / NST; it++) {
            const bool rel = lane < 2 && it < NUNIT / NST - 1;
#pragma unroll
            for (int s = 0; s < NST; s++) {
                const int sn = (s + 1) & (NST - 1);
                const uint32_t pn = (s == NST - 1 ? it + 1 : it) & 1;
                const uint64_t db = mk_desc(vlo0 + (c & 1) * (VBUF >> 4) + g * 16, DB_HI);
                if (g == 0) mbar_wait(bar_vfull + 8 * (c & 1), (c >> 1) & 1);
                uint32_t ok = 1;
#pragma unroll
                for (int kk = 0; kk < 4; kk++) {
                    if (kk == 1) {
                        mbar_arrive_pred(bar_vempty + 8 * ((c & 1) ^ 1), g == 0 && c > 0 && lane == 0);
                        ok = mbar_try(bar_full + 8 * sn, (s == NST - 1 && it == NUNIT / NST - 1) ? (pn ^ 1) : pn);
                    }
                    if (kk == 2 && !ok) mbar_wait(bar_full + 8 * sn, pn);
                    wtransform(g0[kk], raw[kk & 1], tr[kk & 1]);
                    {
                        const uint32_t a = lds_off + (kk < 2 ? s : sn) * WSTAGE + ((kk + 2) & 3) * 1024;
                        ldsm_x4_t(g0[(kk + 2) & 3], a);
                        ldsm_x4_t(raw[kk & 1][0], a + 4096);
                        ldsm_x4_t(raw[kk & 1][1], a + 8192);
                    }
                    mbar_arrive_pred(bar_go + 8 * (s * 4 + kk), threadIdx.x == 0);
                    wgmma_fence();
                    const int sd = (s + kk > 0) ? 1 : it;
                    wgmma_rs_88(m0, g0[kk], db + kk * 2, sd);
                    wgmma_rs_88(m1, tr[kk & 1][0], db + (((1 * VTILE) >> 4) + kk * 2), sd);
                    wgmma_rs_88(m2, tr[kk & 1][1], db + (((2 * VTILE) >> 4) + kk * 2), sd);
                    wgmma_rs_88(m3, tr[kk & 1][2], db + (((3 * VTILE) >> 4) + kk * 2), sd);
                    wgmma_commit();
                    wgmma_wait<1>();
                    if (kk == 3) mbar_arrive_remote_pred(rem_empty + 8 * s, rel);
                }
                if (++g == 5) { g = 0; c++; }
            }
        }
        mbar_wait(bar_vempty, 1);
        wgmma_wait<0>();
#pragma unroll
        for (int j = 0; j < 5; j++) {
            const int i = 24 + 4 * j;
            ex_acc[((0 * 4 + w4) * 5 + j) * 32 + lane] = make_float4(m0[i], m0[i + 1], m0[i + 2], m0[i + 3]);
            ex_acc[((1 * 4 + w4) * 5 + j) * 32 + lane] = make_float4(m1[i], m1[i + 1], m1[i + 2], m1[i + 3]);
            ex_acc[((2 * 4 + w4) * 5 + j) * 32 + lane] = make_float4(m2[i], m2[i + 1], m2[i + 2], m2[i + 3]);
            ex_acc[((3 * 4 + w4) * 5 + j) * 32 + lane] = make_float4(m3[i], m3[i + 1], m3[i + 2], m3[i + 3]);
        }
        asm volatile("bar.arrive 1, 256;" ::: "memory");
        asm volatile("bar.sync 5, 256;" ::: "memory");
        uint32_t pk[3][6];
#pragma unroll
        for (int j = 0; j < 6; j++) {
            const float2 f = ex_m4[((w4 * 2 + 0) * 11 + j) * 32 + lane];
            const float2 gg = ex_m4[((w4 * 2 + 1) * 11 + j) * 32 + lane];
            float y0[4], y1[4], y2[4];
            otrans01(m0 + 4 * j, m1 + 4 * j, m2 + 4 * j, m3 + 4 * j, y0, y1, y2);
            y2[0] += f.x; y2[1] += f.y; y2[2] = fmaf(gg.x, 0.5f, y2[2]); y2[3] = fmaf(gg.y, 0.5f, y2[3]);
            pk[0][j] = gate(y0); pk[1][j] = gate(y1); pk[2][j] = gate(y2);
        }
        finish<2>(pk, slab, gout, tlim, 0, threadIdx.x);
    }
}

typedef CUresult (*EncodeFn)(CUtensorMap*, CUtensorMapDataType, cuuint32_t, void*, const cuuint64_t*, const cuuint64_t*,
                             const cuuint32_t*, const cuuint32_t*, CUtensorMapInterleave, CUtensorMapSwizzle,
                             CUtensorMapL2promotion, CUtensorMapFloatOOBfill);

}

extern "C" void kernel_launch(void* const* d_in, const int* in_sizes, int n_in, void* d_out, int out_size) {
    static EncodeFn enc = nullptr;
    static void* vptr = nullptr;
    if (!enc) {
        void* fn = nullptr;
        cudaDriverEntryPointQueryResult qres;
        cudaGetDriverEntryPoint("cuTensorMapEncodeTiled", &fn, cudaEnableDefault, &qres);
        enc = (EncodeFn)fn;
        cudaFuncSetAttribute(conv_kernel, cudaFuncAttributeMaxDynamicSharedMemorySize, SM_TOTAL);
        cudaGetSymbolAddress(&vptr, g_V);
    }
    CUtensorMap mv, mw;
    {
        cuuint64_t dims[4] = {(cuuint64_t)D_, (cuuint64_t)VROWS, 5, 8};
        cuuint64_t strides[3] = {(cuuint64_t)D_ * 2, (cuuint64_t)D_ * 2 * VROWS, (cuuint64_t)D_ * 2 * VROWS * 5};
        cuuint32_t box[4] = {64, (cuuint32_t)VROWS, 5, 1};
        cuuint32_t es[4] = {1, 1, 1, 1};
        enc(&mv, CU_TENSOR_MAP_DATA_TYPE_BFLOAT16, 4, vptr, dims, strides, box, es, CU_TENSOR_MAP_INTERLEAVE_NONE,
            CU_TENSOR_MAP_SWIZZLE_128B, CU_TENSOR_MAP_L2_PROMOTION_L2_128B, CU_TENSOR_MAP_FLOAT_OOB_FILL_NONE);
    }
    {
        cuuint64_t dims[3] = {1024, (cuuint64_t)D_, 15};
        cuuint64_t strides[2] = {2048, (cuuint64_t)2048 * D_};
        cuuint32_t box[3] = {32, 64, 3};
        cuuint32_t es[3] = {1, 1, 1};
        enc(&mw, CU_TENSOR_MAP_DATA_TYPE_BFLOAT16, 3, d_in[1], dims, strides, box, es, CU_TENSOR_MAP_INTERLEAVE_NONE,
            CU_TENSOR_MAP_SWIZZLE_64B, CU_TENSOR_MAP_L2_PROMOTION_L2_128B, CU_TENSOR_MAP_FLOAT_OOB_FILL_NONE);
    }
    conv_kernel<<<128, NTHREADS, SM_TOTAL>>>(mv, mw, (const __nv_bfloat16*)d_in[0], (__nv_bfloat16*)d_out);
}
```
